```python
import torch

def _softmax(x, axis=-1):
    return torch.softmax(x, dim=axis)
def _gelu(x):
    return torch.nn.functional.gelu(x, approximate="tanh")
def _silu(x):
    return torch.nn.functional.silu(x)
def _sigmoid(x):
    return torch.sigmoid(x)
def _layernorm(x, axis=-1, eps=1e-5):
    m = x.mean(dim=axis, keepdim=True)
    v = x.var(dim=axis, keepdim=True, unbiased=False)
    return (x - m) / torch.sqrt(v + eps)
def _scatter_add(tgt, idx, src, axis=0):
    return tgt.clone().index_add_(axis, idx, src)
def _segment_sum(src, seg, n):
    out = torch.zeros((n,) + src.shape[1:], dtype=src.dtype)
    return out.index_add_(0, seg, src)
def _pad(x, pw):
    flat = tuple(v for pair in reversed(pw) for v in pair)
    return torch.nn.functional.pad(x, flat)

kernel_name = 'standalone__gqa_softmax__prompt'

def setup_inputs():

    _w = (lambda a: (lambda t: t.to(torch.bfloat16) if t.is_floating_point() else t)(torch.as_tensor(a)))
    B, Hq, Hkv, Sq, Sk, D = 1, 32, 32, 2048, 2048, 192
    return {
        "q": _w((lambda *s: torch.randn(*s, dtype=torch.bfloat16) * 0.8)(B, Hq, Sq, D)),
        "k": _w((lambda *s: torch.randn(*s, dtype=torch.bfloat16) * 0.8)(B, Hkv, Sk, D)),
        "v": _w((lambda *s: torch.randn(*s, dtype=torch.bfloat16) * 0.05)(B, Hkv, Sk, D)),
    }

def reference(q, k, v):
    B, Hq, Sq, D = q.shape
    Hkv = k.shape[1]
    rep = Hq // Hkv
    k = (lambda x, n, axis: torch.repeat_interleave(x, n, dim=axis))(k, rep, axis=1)
    v = (lambda x, n, axis: torch.repeat_interleave(x, n, dim=axis))(v, rep, axis=1)
    scale = D ** -0.5
    scores = torch.einsum("bhqd,bhkd->bhqk", q, k) * scale
    p = _softmax(scores, axis=-1)
    return torch.einsum("bhqk,bhkd->bhqd", p, v)
```

```cpp
#include <cuda_runtime.h>
#include <cuda_bf16.h>
#include <cuda.h>
#include <stdint.h>

namespace {

constexpr int NHEAD = 32;
constexpr int SEQ = 2048;
constexpr int HD = 192;
constexpr int BM = 128;
constexpr int BN = 128;
constexpr int NTILES = NHEAD * SEQ / BM;
constexpr int SLOT_BYTES = BN * HD * 2;
constexpr int NSLOT = 3;
constexpr int QW_BYTES = 64 * HD * 2;
constexpr int SM_Q = 0;
constexpr int SM_KV = 2 * QW_BYTES;
constexpr int SM_STG = SM_KV + NSLOT * SLOT_BYTES;
constexpr int SM_BAR = SM_STG + 4 * 8192;
constexpr int SM_STAT = SM_BAR + 256;
constexpr int SMEM_BYTES = SM_STAT + 1024 + 1024;
constexpr int NTHREADS = 384;
constexpr int CL = 2;
constexpr int MAXCL = 66;

struct Sched {
    unsigned long long w[MAXCL];
};
__device__ unsigned int g_claim;
__device__ __align__(16) float2 g_stat[NHEAD * SEQ];
__device__ __align__(16) unsigned int g_flag[NHEAD * SEQ / BM];

__device__ __forceinline__ void wgmma_ss_n128(float (&d)[64], uint64_t da, uint64_t db, int scale_d) {
    asm volatile("{\n.reg .pred p;\nsetp.ne.b32 p, %66, 0;\n"
        "wgmma.mma_async.sync.aligned.m64n128k16.f32.bf16.bf16 "
        "{%0, %1, %2, %3, %4, %5, %6, %7, %8, %9, %10, %11, %12, %13, %14, %15, %16, %17, %18, %19, %20, %21, %22, %23, %24, %25, %26, %27, %28, %29, %30, %31, %32, %33, %34, %35, %36, %37, %38, %39, %40, %41, %42, %43, %44, %45, %46, %47, %48, %49, %50, %51, %52, %53, %54, %55, %56, %57, %58, %59, %60, %61, %62, %63}, "
        "%64, %65, p, 1, 1, 0, 0;\n}\n"
        : "+f"(d[0]), "+f"(d[1]), "+f"(d[2]), "+f"(d[3]), "+f"(d[4]), "+f"(d[5]), "+f"(d[6]), "+f"(d[7]), "+f"(d[8]), "+f"(d[9]), "+f"(d[10]), "+f"(d[11]), "+f"(d[12]), "+f"(d[13]), "+f"(d[14]), "+f"(d[15]), "+f"(d[16]), "+f"(d[17]), "+f"(d[18]), "+f"(d[19]), "+f"(d[20]), "+f"(d[21]), "+f"(d[22]), "+f"(d[23]), "+f"(d[24]), "+f"(d[25]), "+f"(d[26]), "+f"(d[27]), "+f"(d[28]), "+f"(d[29]), "+f"(d[30]), "+f"(d[31]), "+f"(d[32]), "+f"(d[33]), "+f"(d[34]), "+f"(d[35]), "+f"(d[36]), "+f"(d[37]), "+f"(d[38]), "+f"(d[39]), "+f"(d[40]), "+f"(d[41]), "+f"(d[42]), "+f"(d[43]), "+f"(d[44]), "+f"(d[45]), "+f"(d[46]), "+f"(d[47]), "+f"(d[48]), "+f"(d[49]), "+f"(d[50]), "+f"(d[51]), "+f"(d[52]), "+f"(d[53]), "+f"(d[54]), "+f"(d[55]), "+f"(d[56]), "+f"(d[57]), "+f"(d[58]), "+f"(d[59]), "+f"(d[60]), "+f"(d[61]), "+f"(d[62]), "+f"(d[63])
        : "l"(da), "l"(db), "r"(scale_d));
}

__device__ __forceinline__ void wgmma_rs_n192(float (&d)[96], uint32_t a0, uint32_t a1, uint32_t a2, uint32_t a3, uint64_t db, int scale_d) {
    asm volatile("{\n.reg .pred p;\nsetp.ne.b32 p, %101, 0;\n"
        "wgmma.mma_async.sync.aligned.m64n192k16.f32.bf16.bf16 "
        "{%0, %1, %2, %3, %4, %5, %6, %7, %8, %9, %10, %11, %12, %13, %14, %15, %16, %17, %18, %19, %20, %21, %22, %23, %24, %25, %26, %27, %28, %29, %30, %31, %32, %33, %34, %35, %36, %37, %38, %39, %40, %41, %42, %43, %44, %45, %46, %47, %48, %49, %50, %51, %52, %53, %54, %55, %56, %57, %58, %59, %60, %61, %62, %63, %64, %65, %66, %67, %68, %69, %70, %71, %72, %73, %74, %75, %76, %77, %78, %79, %80, %81, %82, %83, %84, %85, %86, %87, %88, %89, %90, %91, %92, %93, %94, %95}, "
        "{%96, %97, %98, %99}, %100, p, 1, 1, 1;\n}\n"
        : "+f"(d[0]), "+f"(d[1]), "+f"(d[2]), "+f"(d[3]), "+f"(d[4]), "+f"(d[5]), "+f"(d[6]), "+f"(d[7]), "+f"(d[8]), "+f"(d[9]), "+f"(d[10]), "+f"(d[11]), "+f"(d[12]), "+f"(d[13]), "+f"(d[14]), "+f"(d[15]), "+f"(d[16]), "+f"(d[17]), "+f"(d[18]), "+f"(d[19]), "+f"(d[20]), "+f"(d[21]), "+f"(d[22]), "+f"(d[23]), "+f"(d[24]), "+f"(d[25]), "+f"(d[26]), "+f"(d[27]), "+f"(d[28]), "+f"(d[29]), "+f"(d[30]), "+f"(d[31]), "+f"(d[32]), "+f"(d[33]), "+f"(d[34]), "+f"(d[35]), "+f"(d[36]), "+f"(d[37]), "+f"(d[38]), "+f"(d[39]), "+f"(d[40]), "+f"(d[41]), "+f"(d[42]), "+f"(d[43]), "+f"(d[44]), "+f"(d[45]), "+f"(d[46]), "+f"(d[47]), "+f"(d[48]), "+f"(d[49]), "+f"(d[50]), "+f"(d[51]), "+f"(d[52]), "+f"(d[53]), "+f"(d[54]), "+f"(d[55]), "+f"(d[56]), "+f"(d[57]), "+f"(d[58]), "+f"(d[59]), "+f"(d[60]), "+f"(d[61]), "+f"(d[62]), "+f"(d[63]), "+f"(d[64]), "+f"(d[65]), "+f"(d[66]), "+f"(d[67]), "+f"(d[68]), "+f"(d[69]), "+f"(d[70]), "+f"(d[71]), "+f"(d[72]), "+f"(d[73]), "+f"(d[74]), "+f"(d[75]), "+f"(d[76]), "+f"(d[77]), "+f"(d[78]), "+f"(d[79]), "+f"(d[80]), "+f"(d[81]), "+f"(d[82]), "+f"(d[83]), "+f"(d[84]), "+f"(d[85]), "+f"(d[86]), "+f"(d[87]), "+f"(d[88]), "+f"(d[89]), "+f"(d[90]), "+f"(d[91]), "+f"(d[92]), "+f"(d[93]), "+f"(d[94]), "+f"(d[95])
        : "r"(a0), "r"(a1), "r"(a2), "r"(a3), "l"(db), "r"(scale_d));
}

__device__ __forceinline__ void wg_fence() { asm volatile("wgmma.fence.sync.aligned;\n" ::: "memory"); }
__device__ __forceinline__ void wg_commit() { asm volatile("wgmma.commit_group.sync.aligned;\n" ::: "memory"); }
template <int N> __device__ __forceinline__ void wg_wait() { asm volatile("wgmma.wait_group.sync.aligned %0;\n" ::"n"(N) : "memory"); }
template <int N> __device__ __forceinline__ void fence_f(float (&d)[N]) {
#pragma unroll
    for (int i = 0; i < N; i++) asm volatile("" : "+f"(d[i])::"memory");
}
template <int N> __device__ __forceinline__ void fence_u(uint32_t (&d)[N]) {
#pragma unroll
    for (int i = 0; i < N; i++) asm volatile("" : "+r"(d[i])::"memory");
}

__device__ __forceinline__ void mbar_init(uint32_t bar, uint32_t cnt) {
    asm volatile("mbarrier.init.shared::cta.b64 [%0], %1;\n" ::"r"(bar), "r"(cnt) : "memory");
}
__device__ __forceinline__ void mbar_wait(uint32_t bar, uint32_t parity) {
    asm volatile("{\n.reg .pred p;\n.reg .u32 n;\nmov.u32 n, 0;\n"
                 "WAIT_LOOP:\n"
                 "mbarrier.try_wait.parity.shared::cta.b64 p, [%0], %1;\n"
                 "@p bra WAIT_DONE;\n"
                 "add.u32 n, n, 1;\n"
                 "setp.lt.u32 p, n, 4194304;\n"
                 "@p bra WAIT_LOOP;\n"
                 "trap;\n"
                 "WAIT_DONE:\n}\n" ::"r"(bar), "r"(parity) : "memory");
}
__device__ __forceinline__ bool mbar_test(uint32_t bar, uint32_t parity) {
    uint32_t ok;
    asm volatile("{\n.reg .pred p;\nmbarrier.test_wait.parity.shared::cta.b64 p, [%1], %2;\nselp.u32 %0, 1, 0, p;\n}\n"
                 : "=r"(ok) : "r"(bar), "r"(parity) : "memory");
    return ok != 0;
}
__device__ __forceinline__ void mbar_wait_long(uint32_t bar, uint32_t parity) {
    asm volatile("{\n.reg .pred p;\n.reg .u32 n;\nmov.u32 n, 0;\n"
                 "WAIT_LOOP:\n"
                 "mbarrier.try_wait.parity.shared::cta.b64 p, [%0], %1, 100000;\n"
                 "@p bra WAIT_DONE;\n"
                 "add.u32 n, n, 1;\n"
                 "setp.lt.u32 p, n, 262144;\n"
                 "@p bra WAIT_LOOP;\n"
                 "trap;\n"
                 "WAIT_DONE:\n}\n" ::"r"(bar), "r"(parity) : "memory");
}
__device__ __forceinline__ void flag_wait(const unsigned int* flag) {
    asm volatile("{\n.reg .pred p;\n.reg .u32 n, v;\nmov.u32 n, 0;\n"
                 "FLAG_LOOP:\n"
                 "ld.acquire.gpu.global.u32 v, [%0];\n"
                 "setp.eq.u32 p, v, 2;\n"
                 "@p bra FLAG_DONE;\n"
                 "nanosleep.u32 200;\n"
                 "add.u32 n, n, 1;\n"
                 "setp.lt.u32 p, n, 16777216;\n"
                 "@p bra FLAG_LOOP;\n"
                 "trap;\n"
                 "FLAG_DONE:\n}\n" ::"l"(flag) : "memory");
}
__device__ __forceinline__ void mbar_expect_tx(uint32_t bar, uint32_t bytes) {
    asm volatile("mbarrier.arrive.expect_tx.shared::cta.b64 _, [%0], %1;\n" ::"r"(bar), "r"(bytes) : "memory");
}
__device__ __forceinline__ void mbar_arrive(uint32_t bar) {
    asm volatile("mbarrier.arrive.shared::cta.b64 _, [%0];\n" ::"r"(bar) : "memory");
}
__device__ __forceinline__ void mbar_arrive_cluster(uint32_t bar, uint32_t cta) {
    asm volatile("{\n.reg .b32 ra;\nmapa.shared::cluster.u32 ra, %0, %1;\n"
                 "mbarrier.arrive.shared::cluster.b64 _, [ra];\n}\n" ::"r"(bar), "r"(cta) : "memory");
}
__device__ __forceinline__ void tma_load(uint32_t dst, const CUtensorMap* map, int c0, int c1, uint32_t bar) {
    asm volatile("cp.async.bulk.tensor.2d.shared::cluster.global.mbarrier::complete_tx::bytes [%0], [%1, {%2, %3}], [%4];\n"
                 ::"r"(dst), "l"(map), "r"(c0), "r"(c1), "r"(bar) : "memory");
}
__device__ __forceinline__ void tma_load_mc(uint32_t dst, const CUtensorMap* map, int c0, int c1, uint32_t bar, uint16_t mask) {
    asm volatile("cp.async.bulk.tensor.2d.shared::cluster.global.mbarrier::complete_tx::bytes.multicast::cluster [%0], [%1, {%2, %3}], [%4], %5;\n"
                 ::"r"(dst), "l"(map), "r"(c0), "r"(c1), "r"(bar), "h"(mask) : "memory");
}
__device__ __forceinline__ void tma_store(const CUtensorMap* map, int c0, int c1, uint32_t src) {
    asm volatile("cp.async.bulk.tensor.2d.global.shared::cta.bulk_group [%0, {%1, %2}], [%3];\n"
                 "cp.async.bulk.commit_group;\n" ::"l"(map), "r"(c0), "r"(c1), "r"(src) : "memory");
}
template <int N> __device__ __forceinline__ void tma_store_wait_read() {
    asm volatile("cp.async.bulk.wait_group.read %0;\n" ::"n"(N) : "memory");
}
__device__ __forceinline__ void bulk_load(uint32_t dst, const void* p, uint32_t bytes, uint32_t bar) {
    asm volatile("cp.async.bulk.shared::cluster.global.mbarrier::complete_tx::bytes [%0], [%1], %2, [%3];\n"
                 ::"r"(dst), "l"(p), "r"(bytes), "r"(bar) : "memory");
}
__device__ __forceinline__ void bulk_prefetch(const void* p, uint32_t bytes) {
    asm volatile("cp.async.bulk.prefetch.L2.global [%0], %1;\n" ::"l"(p), "r"(bytes) : "memory");
}
__device__ __forceinline__ void prefetch_map(const CUtensorMap* map) {
    asm volatile("prefetch.tensormap [%0];\n" ::"l"(map) : "memory");
}
__device__ __forceinline__ void bar_sync(uint32_t id) { asm volatile("bar.sync %0, 256;\n" ::"r"(id) : "memory"); }
__device__ __forceinline__ void bar_arrive(uint32_t id) { asm volatile("bar.arrive %0, 256;\n" ::"r"(id) : "memory"); }
__device__ __forceinline__ void sched_fence(int z) {
    asm volatile("{\n.reg .pred p;\nsetp.ne.s32 p, %0, 0;\nSF_LOOP:\n@p st.volatile.shared.u32 [%0], %0;\n@p bra.uni SF_LOOP;\n}\n" ::"r"(z) : "memory");
}
__device__ __forceinline__ float ex2(float x) {
    float y;
    asm("ex2.approx.ftz.f32 %0, %1;\n" : "=f"(y) : "f"(x));
    return y;
}
__device__ __forceinline__ uint32_t pack_bf16(float lo, float hi) {
    uint32_t r;
    asm("cvt.rn.bf16x2.f32 %0, %1, %2;\n" : "=r"(r) : "f"(hi), "f"(lo));
    return r;
}
__device__ __forceinline__ float pack_bf16_f(float lo, float hi) {
    float r;
    asm("{\n.reg .b32 t;\ncvt.rn.bf16x2.f32 t, %1, %2;\nmov.b32 %0, t;\n}\n" : "=f"(r) : "f"(hi), "f"(lo));
    return r;
}
constexpr uint32_t DESC_HI = (1024u >> 4) | (1u << 30);
__device__ __forceinline__ uint64_t mk_desc(uint32_t lo) { return ((uint64_t)DESC_HI << 32) | lo; }

__device__ __forceinline__ void issue_s(float (&S)[64], uint32_t qlo, uint32_t klo) {
    wg_fence();
#pragma unroll
    for (int k = 0; k < 12; k++) {
        wgmma_ss_n128(S, mk_desc(qlo + (k >> 2) * (8192 >> 4) + (k & 3) * 2), mk_desc(klo + (k >> 2) * (16384 >> 4) + (k & 3) * 2), k > 0);
    }
    wg_commit();
}
__device__ __forceinline__ void issue_pv(float (&O)[96], uint32_t (&P)[32], uint32_t vlo, int acc) {
    wg_fence();
#pragma unroll
    for (int k = 0; k < 8; k++) {
        wgmma_rs_n192(O, P[4 * k], P[4 * k + 1], P[4 * k + 2], P[4 * k + 3], mk_desc(vlo + k * (2048 >> 4)), k > 0 ? 1 : acc);
    }
    wg_commit();
}

constexpr float SCALE_LOG2 = 0.07216878364870322f * 1.4426950408889634f;
constexpr int NA1 = 9;
constexpr int NA2 = 2;
constexpr int NMAX = 8;
constexpr float SUM_LIMIT = 65536.0f;
constexpr int CLAIM_U = 24;

template <int J0, int J1>
__device__ __forceinline__ void exp_range(float (&S)[64], float nb0, float nb1, float& s0, float& s1) {
#pragma unroll
    for (int j = J0; j < J1; j++) {
        S[4 * j] = ex2(fmaf(S[4 * j], SCALE_LOG2, nb0));
        S[4 * j + 1] = ex2(fmaf(S[4 * j + 1], SCALE_LOG2, nb0));
        S[4 * j + 2] = ex2(fmaf(S[4 * j + 2], SCALE_LOG2, nb1));
        S[4 * j + 3] = ex2(fmaf(S[4 * j + 3], SCALE_LOG2, nb1));
        s0 += S[4 * j] + S[4 * j + 1];
        s1 += S[4 * j + 2] + S[4 * j + 3];
    }
}
template <int NT>
__device__ __forceinline__ void row_max(const float (&S)[64], float& x0, float& x1) {
    float y0 = S[1], y1 = S[3];
    x0 = S[0];
    x1 = S[2];
#pragma unroll
    for (int j = 1; j < NT; j++) {
        x0 = fmaxf(x0, S[4 * j]);
        y0 = fmaxf(y0, S[4 * j + 1]);
        x1 = fmaxf(x1, S[4 * j + 2]);
        y1 = fmaxf(y1, S[4 * j + 3]);
    }
    x0 = fmaxf(x0, y0);
    x1 = fmaxf(x1, y1);
    x0 = fmaxf(x0, __shfl_xor_sync(0xffffffffu, x0, 1));
    x1 = fmaxf(x1, __shfl_xor_sync(0xffffffffu, x1, 1));
    x0 = fmaxf(x0, __shfl_xor_sync(0xffffffffu, x0, 2));
    x1 = fmaxf(x1, __shfl_xor_sync(0xffffffffu, x1, 2));
}
__device__ __forceinline__ void recompute_s(float (&S)[64], const __nv_bfloat16* qrow, const __nv_bfloat16* krow) {
#pragma unroll
    for (int i = 0; i < 64; i++) S[i] = 0.f;
#pragma unroll 1
    for (int k = 0; k < 12; k++) {
        const uint32_t a0 = *reinterpret_cast<const uint32_t*>(qrow + k * 16);
        const uint32_t a1 = *reinterpret_cast<const uint32_t*>(qrow + 8 * HD + k * 16);
        const uint32_t a2 = *reinterpret_cast<const uint32_t*>(qrow + k * 16 + 8);
        const uint32_t a3 = *reinterpret_cast<const uint32_t*>(qrow + 8 * HD + k * 16 + 8);
#pragma unroll
        for (int j = 0; j < 16; j++) {
            const uint32_t b0 = *reinterpret_cast<const uint32_t*>(krow + j * 8 * HD + k * 16);
            const uint32_t b1 = *reinterpret_cast<const uint32_t*>(krow + j * 8 * HD + k * 16 + 8);
            asm volatile("mma.sync.aligned.m16n8k16.row.col.f32.bf16.bf16.f32 {%0,%1,%2,%3}, {%4,%5,%6,%7}, {%8,%9}, {%0,%1,%2,%3};\n"
                         : "+f"(S[4 * j]), "+f"(S[4 * j + 1]), "+f"(S[4 * j + 2]), "+f"(S[4 * j + 3])
                         : "r"(a0), "r"(a1), "r"(a2), "r"(a3), "r"(b0), "r"(b1));
        }
    }
}
__device__ __forceinline__ void rescale_o(float (&O)[96], float a0, float a1) {
#pragma unroll
    for (int i = 0; i < 24; i++) {
        O[4 * i] *= a0;
        O[4 * i + 1] *= a0;
        O[4 * i + 2] *= a1;
        O[4 * i + 3] *= a1;
    }
}

__device__ __forceinline__ float quad_sum(float l) {
    l += __shfl_xor_sync(0xffffffffu, l, 1);
    l += __shfl_xor_sync(0xffffffffu, l, 2);
    return l;
}
template <int C, bool SCALE = true>
__device__ __forceinline__ void pack_o(float (&O)[96], float i0, float i1) {
    if (!SCALE) i0 = i1 = 1.0f;
#pragma unroll
    for (int o = 32 * C; o < 32 * C + 32; o += 8) {
        O[o] = pack_bf16_f(O[o] * i0, O[o + 1] * i0);
        O[o + 1] = pack_bf16_f(O[o + 2] * i1, O[o + 3] * i1);
        O[o + 2] = pack_bf16_f(O[o + 4] * i0, O[o + 5] * i0);
        O[o + 3] = pack_bf16_f(O[o + 6] * i1, O[o + 7] * i1);
    }
}
template <int C>
__device__ __forceinline__ void stsm_o(float (&O)[96], uint32_t buf, uint32_t x) {
#pragma unroll
    for (int t = 0; t < 4; t++) {
        const int o = 32 * C + 8 * t;
        asm volatile("stmatrix.sync.aligned.m8n8.x4.shared.b16 [%0], {%1,%2,%3,%4};\n"
                     ::"r"(buf + (x ^ (uint32_t)(t << 5))), "f"(O[o]), "f"(O[o + 1]), "f"(O[o + 2]), "f"(O[o + 3]) : "memory");
    }
}
__device__ __forceinline__ void commit_o(uint32_t bar, int lane) {
    asm volatile("fence.proxy.async.shared::cta;\n" ::: "memory");
    __syncwarp();
    if (lane == 0) mbar_arrive(bar);
}
__device__ __forceinline__ void load_partial(uint32_t (&T)[48], uint32_t buf0, uint32_t buf, uint32_t x) {
#pragma unroll
    for (int t = 0; t < 12; t++) {
        asm volatile("ldmatrix.sync.aligned.m8n8.x4.shared.b16 {%0,%1,%2,%3}, [%4];\n"
                     : "=r"(T[4 * t]), "=r"(T[4 * t + 1]), "=r"(T[4 * t + 2]), "=r"(T[4 * t + 3])
                     : "r"((t < 4 ? buf0 : buf + (t >> 2) * 8192) + (x ^ (uint32_t)((t & 3) << 5))) : "memory");
    }
}
template <int C>
__device__ __forceinline__ void finish_o(float (&O)[96], const uint32_t (&T)[48], float i0, float i1, float k0, float k1, uint32_t stg,
                                         uint32_t x, uint32_t bar_ofull, int lane) {
#pragma unroll
    for (int p = 16 * C; p < 16 * C + 16; p++) {
        const float i = (p & 1) ? i1 : i0, k = (p & 1) ? k1 : k0;
        O[2 * p] = fmaf(__uint_as_float(T[p] << 16), k, O[2 * p] * i);
        O[2 * p + 1] = fmaf(__uint_as_float(T[p] & 0xffff0000u), k, O[2 * p + 1] * i);
    }
    pack_o<C, false>(O, i0, i1);
    stsm_o<C>(O, stg + C * 8192, x);
    commit_o(bar_ofull + 8 * C, lane);
}

__global__ void __launch_bounds__(NTHREADS, 1)
fa_fwd_kernel(const __grid_constant__ CUtensorMap mq, const __grid_constant__ CUtensorMap mk,
              const __grid_constant__ CUtensorMap mv, const __grid_constant__ CUtensorMap mo,
              const __grid_constant__ Sched sched, const __nv_bfloat16* __restrict__ gq, const __nv_bfloat16* __restrict__ gk,
              const __nv_bfloat16* __restrict__ gout, int zero) {
    extern __shared__ uint8_t smem_raw[];
    const uint32_t sb = ((uint32_t)__cvta_generic_to_shared(smem_raw) + 1023u) & ~1023u;
    const uint32_t bar_full = sb + SM_BAR;
    const uint32_t bar_empty = sb + SM_BAR + 32;
    const uint32_t bar_qfull = sb + SM_BAR + 64;
    const uint32_t bar_qempty = sb + SM_BAR + 96;
    const uint32_t bar_ofree = sb + SM_BAR + 128;
    const uint32_t bar_go = sb + SM_BAR + 112;
    const uint32_t bar_merge = sb + SM_BAR + 144;
    const uint32_t bar_ofull = sb + SM_BAR + 160;
    const uint32_t bar_claim = sb + SM_BAR + 24;
    const uint32_t bar_plan = sb + SM_BAR + 56;
    const uint32_t sm_plan = sb + SM_BAR + 80;

    const int warp = __shfl_sync(0xffffffffu, threadIdx.x >> 5, 0);
    const int lane = threadIdx.x & 31;
    const int rank = (int)(blockIdx.x % CL);
    const unsigned int cid = blockIdx.x / CL;
    const unsigned int t0 = cid < 64 ? (cid & 7) * 8 + (cid >> 3) : cid + 64;
    unsigned long long sw = t0 | ((t0 + (cid < 64 ? 64 : 2)) << 8);
    int ucut = 0, uend = 255;
    auto q_row = [&](int seg) { return (int)((sw >> (8 * seg)) & 255) * (CL * BM) + rank * BM; };
    auto kv_row = [&](int u) {
        return (int)((sw >> (8 * (u >> 4) + 3)) & 31) * SEQ + ((u & 15) + ((u | 15) >= uend ? (int)(sw >> 56) & 15 : 0)) * BN;
    };
    auto get_plan = [&]() {
        unsigned long long p;
        asm volatile("ld.shared.u64 %0, [%1];\n" : "=l"(p) : "r"(sm_plan) : "memory");
        sw |= p;
        ucut = (int)(p >> 40) & 255;
        uend = (int)(p >> 48) & 255;
    };

    if (threadIdx.x == 0) {
        bulk_prefetch(gk + (size_t)(kv_row(0) + ((q_row(0) >> 7) & 15) * 8) * HD, 8 * HD * 2);
        bulk_prefetch(gq + (size_t)q_row(0) * HD, QW_BYTES);
    }
    if (warp == 1 && lane == 0) {
        for (int i = 0; i < NSLOT; i++) {
            mbar_init(bar_full + 8 * i, 1);
            mbar_init(bar_empty + 8 * i, 2 * CL);
        }
        for (int i = 0; i < 2; i++) {
            mbar_init(bar_qfull + 8 * i, 1);
            mbar_init(bar_qempty + 8 * i, 1);
            mbar_init(bar_merge + 8 * i, 1);
            mbar_init(bar_go + 8 * i, 1);
        }
        mbar_init(bar_claim, 1);
        mbar_init(bar_plan, 1);
        mbar_init(bar_ofree, 2);
        mbar_init(bar_ofree + 8, 1);
        for (int i = 0; i < 6; i++) mbar_init(bar_ofull + 8 * i, 4);
        asm volatile("fence.mbarrier_init.release.cluster;\n" ::: "memory");
        asm volatile("fence.proxy.async.shared::cta;\n" ::: "memory");
        const int row0 = kv_row(0), qrow0 = q_row(0);
        mbar_expect_tx(bar_full, SLOT_BYTES);
        mbar_expect_tx(bar_qfull, QW_BYTES);
        mbar_expect_tx(bar_qfull + 8, QW_BYTES);
#pragma unroll
        for (int c = 0; c < 3; c++) {
            tma_load(sb + SM_KV + c * 16384, &mk, c * 64, row0, bar_full);
            tma_load(sb + SM_KV + c * 16384 + 8192, &mk, c * 64, row0 + 64, bar_full);
            tma_load(sb + SM_Q + c * 8192, &mq, c * 64, qrow0, bar_qfull);
        }
#pragma unroll
        for (int c = 0; c < 3; c++) tma_load(sb + SM_Q + QW_BYTES + c * 8192, &mq, c * 64, qrow0 + 64, bar_qfull + 8);
        mbar_expect_tx(bar_plan, 8);
    }
    if (blockIdx.x == 0 && warp == 3) {
#pragma unroll
        for (int i = 0; i < NTILES / 128; i++) reinterpret_cast<uint4*>(g_flag)[i * 32 + lane] = make_uint4(0, 0, 0, 0);
        if (lane == 0) g_claim = 0;
    }
    if (warp == 2 && lane == 0) {
        prefetch_map(&mv);
        prefetch_map(&mo);
    }
    __syncwarp();
    asm volatile("barrier.cluster.arrive.relaxed.aligned;\n" ::: "memory");
    asm volatile("barrier.cluster.wait.aligned;\n" ::: "memory");

    if (warp < 4) {
        asm volatile("setmaxnreg.dec.sync.aligned.u32 24;\n");
        if (warp == 1 && lane == 0) {
            constexpr int ROWS = BN / CL;
            int slot = 1;
            uint32_t phase = 1;
            int uv = 0;
#pragma unroll 1
            for (int n = 1;; n++) {
                const int uk = ((uv & 15) == 15 || uv == ucut - (ucut == 0)) ? (uv | 15) + 1 : uv + 1;
                const bool isk = n & 1;
                if (isk) {
                    if (uk == CLAIM_U && rank == 0) mbar_arrive(bar_claim);
                    if (uk == CLAIM_U + 3) {
                        mbar_wait_long(bar_plan, 0);
                        get_plan();
                    }
                    if (uk >= uend) continue;
                }
                const int row = kv_row(isk ? uk : uv) + rank * ROWS;
                const CUtensorMap* mp = isk ? &mk : &mv;
                const uint32_t fb = bar_full + 8 * slot;
                mbar_wait_long(bar_empty + 8 * slot, phase);
                mbar_expect_tx(fb, SLOT_BYTES);
                const uint32_t dst = sb + SM_KV + slot * SLOT_BYTES + rank * ROWS * 128;
#pragma unroll
                for (int c = 0; c < 3; c++) tma_load_mc(dst + c * 16384, mp, c * 64, row, fb, (uint16_t)((1 << CL) - 1));
                if (++slot == NSLOT) { slot = 0; phase ^= 1; }
                if (!isk) {
                    if (uk >= uend) break;
                    const int left = (((uv >> 4) == 2 && ucut) ? ucut : (uv | 15)) - uv;
                    const int hi = min(6 - left, 4), lo = (uv & 15) ? 5 - left : 0;
                    if ((uv | 15) + 1 < uend && lo >= 0 && hi > lo)
                        bulk_prefetch(gq + (size_t)q_row((uv >> 4) + 1) * HD + lo * 6144, (hi - lo) * 12288);
                    if (uv == uend - 8) mbar_arrive(bar_go);
                    uv = uk;
                }
            }
            mbar_wait_long(bar_empty + 8 * slot, phase);
            mbar_arrive(bar_go + 8);
        } else if (warp == 0 && lane == 0) {
            if (rank == 0) {
                mbar_wait_long(bar_claim, 0);
                const unsigned int idx = atomicAdd(&g_claim, 1u);
                if (idx == gridDim.x / CL - 1) g_claim = 0;
                const unsigned long long p = sched.w[idx];
#pragma unroll
                for (int r = 0; r < CL; r++)
                    asm volatile("{\n.reg .b32 ra, rb;\nmapa.shared::cluster.u32 ra, %0, %2;\nmapa.shared::cluster.u32 rb, %1, %2;\n"
                                 "st.async.weak.shared::cluster.mbarrier::complete_tx::bytes.b64 [ra], %3, [rb];\n}\n"
                                 ::"r"(sm_plan), "r"(bar_plan), "r"(r), "l"(p) : "memory");
            }
            mbar_wait_long(bar_plan, 0);
            get_plan();
            const int nseg = ((uend - 1) >> 4) + 1;
            const int row = q_row(nseg - 1);
            const uint32_t tailbuf = sb + SM_KV + (uint32_t)(sw >> 60) * SLOT_BYTES;
            mbar_wait_long(bar_go, 0);
            if (uend & 15) {
                flag_wait(g_flag + (row >> 7));
                g_flag[row >> 7] = 0;
                asm volatile("fence.proxy.async;\n" ::: "memory");
                bulk_prefetch(gout + (size_t)(row + 64) * HD, QW_BYTES);
                mbar_wait_long(bar_ofree, nseg & 1);
                mbar_expect_tx(bar_merge, QW_BYTES + 512);
                mbar_expect_tx(bar_merge + 8, QW_BYTES + 512);
                bulk_load(sb + SM_STAT, g_stat + row, 512, bar_merge);
                bulk_load(sb + SM_STAT + 512, g_stat + row + 64, 512, bar_merge + 8);
#pragma unroll
                for (int c = 0; c < 4; c++) tma_load(sb + SM_STG + c * 8192, &mo, (c % 3) * 64, row + (c / 3) * 64, bar_merge + 8 * (c / 3));
                mbar_wait_long(bar_go + 8, 0);
                tma_load(tailbuf, &mo, 64, row + 64, bar_merge + 8);
                tma_load(tailbuf + 8192, &mo, 128, row + 64, bar_merge + 8);
            } else {
                mbar_wait_long(bar_ofree, nseg & 1);
                mbar_arrive(bar_merge);
                mbar_arrive(bar_merge + 8);
            }
        } else if (warp >= 2 && lane == 0) {
            const int w = warp & 1;
#pragma unroll 1
            for (int i = 0; 16 * i < uend; i++) {
                if (i == 1) {
                    mbar_wait_long(bar_plan, 0);
                    get_plan();
                }
                const int row = q_row(i) + w * 64;
                const bool last = (16 * i + 16 >= uend);
                const uint32_t tailbuf = sb + SM_KV + (uint32_t)(sw >> 60) * SLOT_BYTES - 8192;
                auto next_q = [&](int seg) {
                    mbar_wait_long(bar_qempty + 8 * w, seg & 1);
                    mbar_expect_tx(bar_qfull + 8 * w, QW_BYTES);
                    const int nrow = q_row(seg + 1) + w * 64;
#pragma unroll
                    for (int c = 0; c < 3; c++) tma_load(sb + SM_Q + w * QW_BYTES + c * 8192, &mq, c * 64, nrow, bar_qfull + 8 * w);
                };
                if (!last && !(i == 2 && ucut == 33)) next_q(i);
#pragma unroll
                for (int c = 0; c < 3; c++) {
                    mbar_wait_long(bar_ofull + 24 * w + 8 * c, i & 1);
                    tma_store(&mo, c * 64, row, (last && w == 1 && c > 0) ? tailbuf + c * 8192 : sb + SM_STG + ((c + 3 * w) & 3) * 8192);
                    if (c == 1 && w == 0 && !last) {
                        tma_store_wait_read<0>();
                        mbar_arrive(bar_ofree + 8);
                    }
                }
                if (i == 1 && ucut == 33) next_q(2);
                tma_store_wait_read<0>();
                mbar_arrive(bar_ofree);
                if (i == 2 && ucut != 0) {
                    asm volatile("cp.async.bulk.wait_group 0;\n" ::: "memory");
                    asm volatile("fence.proxy.async;\n" ::: "memory");
                    __threadfence();
                    asm volatile("red.release.gpu.global.add.u32 [%0], 1;\n" ::"l"(g_flag + (row >> 7)) : "memory");
                }
            }
        }
    } else {
        asm volatile("setmaxnreg.inc.sync.aligned.u32 240;\n");
        const int wg = (warp >> 2) - 1;
        const int wq = warp & 3;
        const uint32_t mybar = 1 + wg, otherbar = 2 - wg;
        const uint32_t qlo = ((sb + SM_Q + wg * QW_BYTES) & 0x3FFFF) >> 4;
        const uint32_t kvlo = ((sb + SM_KV) & 0x3FFFF) >> 4;
        const uint32_t stg = sb + SM_STG + (wq * 16 + (lane & 15)) * 128;
        const uint32_t stx = (uint32_t)(((lane >> 4) ^ (lane & 7)) << 4);
        constexpr uint32_t VLBO = (16384u >> 4) << 16;
        const bool sig = (wq == 1) && (lane < CL);
        float O[96], S[64];
        uint32_t P[32];
        bool resc = false;
        float nb0, nb1, l0, l1, a0 = 1.f, a1 = 1.f, lp0 = 0.f, lp1 = 0.f;
        int slot = 0;
        uint32_t phase = 0;

        auto release = [&](int s) {
            if (sig) mbar_arrive_cluster(bar_empty + 8 * s, lane);
        };
        auto advance = [&]() { if (++slot == NSLOT) { slot = 0; phase ^= 1; } };

        mbar_wait(bar_qfull + 8 * wg, 0);
        mbar_wait(bar_full, 0);
        if (wg == 1) bar_sync(mybar);
        issue_s(S, qlo, kvlo);
        bar_arrive(otherbar);
        wg_wait<0>();
        fence_f(S);
        release(slot);
        advance();
        row_max<16>(S, nb0, nb1);
        nb0 *= -SCALE_LOG2;
        nb1 *= -SCALE_LOG2;
        l0 = 0.f;
        l1 = 0.f;
        exp_range<0, 16>(S, nb0, nb1, l0, l1);
#pragma unroll
        for (int i = 0; i < 32; i++) P[i] = pack_bf16(S[2 * i], S[2 * i + 1]);
        mbar_wait(bar_full + 8 * slot, phase);

#pragma unroll 1
        for (int u = 1; u < uend;) {
            const int j = u & 15;
            const bool seg_end = (j == 15) || (u == ucut);
            const int unext = seg_end ? (u | 15) + 1 : u + 1;
            const int kslot = slot;
            bar_sync(mybar);
            fence_f(S);
            issue_s(S, qlo, kvlo + slot * (SLOT_BYTES >> 4));
            bar_arrive(otherbar);
            advance();
            const bool vok = mbar_test(bar_full + 8 * slot, phase);
            if (j == 1) {
                if (u > 16) {
                    pack_o<2>(O, lp0, lp1);
                    if (wg == 1) {
                        mbar_wait(bar_ofree + 8, ((u >> 4) ^ 1) & 1);
                        stsm_o<1>(O, stg, stx);
                    }
                    stsm_o<2>(O, stg + (2 - wg) * 8192, stx);
                    asm volatile("fence.proxy.async.shared::cta;\n" ::: "memory");
                    __syncwarp();
                    if (lane <= wg) mbar_arrive(bar_ofull + 24 * wg + 16 - 8 * lane);
                }
            } else {
                if (resc) rescale_o(O, a0, a1);
                if (j == 0) {
                    l0 = quad_sum(l0);
                    l1 = quad_sum(l1);
                    lp0 = __fdividef(1.0f, l0);
                    lp1 = __fdividef(1.0f, l1);
                    if (u == 48 && ucut != 0 && (lane & 3) == 0) {
                        float2* st = g_stat + q_row(2) + wg * 64 + wq * 16 + (lane >> 2);
                        st[0] = make_float2(nb0, l0);
                        st[8] = make_float2(nb1, l1);
                    }
                    mbar_wait(bar_ofree, (u >> 4) & 1);
                }
            }
            wg_wait<0>();
            fence_f(S);
            release(kslot);
            if (seg_end && wq == 1 && lane == 0) mbar_arrive(bar_qempty + 8 * wg);
            if (j == 0) {
                row_max<NMAX>(S, nb0, nb1);
                nb0 *= -SCALE_LOG2;
                nb1 *= -SCALE_LOG2;
                l0 = 0.f; l1 = 0.f;
            }
            float s0 = 0.f, s1 = 0.f;
            const bool pre = (wg == 0);
            exp_range<0, NA2>(S, nb0, nb1, s0, s1);
            if (pre) exp_range<NA2, NA1>(S, nb0, nb1, s0, s1);
            if (!vok) mbar_wait(bar_full + 8 * slot, phase);
            bar_sync(mybar);
            fence_f(O);
            fence_u(P);
            issue_pv(O, P, (kvlo + slot * (SLOT_BYTES >> 4)) | VLBO, j != 1);
            bar_arrive(otherbar);
            const int vslot = slot;
            advance();
            sched_fence(zero);
            const bool kok = mbar_test(bar_full + 8 * slot, phase);
            if (!pre) exp_range<NA2, NA1>(S, nb0, nb1, s0, s1);
            exp_range<NA1, 16>(S, nb0, nb1, s0, s1);
            resc = __any_sync(0xffffffffu, !(s0 <= SUM_LIMIT && s1 <= SUM_LIMIT));
            if (resc) {
                float x0, x1;
                row_max<16>(S, x0, x1);
                if (__any_sync(0xffffffffu, !(s0 <= 1.0e36f && s1 <= 1.0e36f))) {
                    recompute_s(S, gq + (size_t)(q_row(u >> 4) + wg * 64 + wq * 16 + (lane >> 2)) * HD + (lane & 3) * 2,
                                gk + (size_t)(kv_row(u) + (lane >> 2)) * HD + (lane & 3) * 2);
                    row_max<16>(S, x0, x1);
                    x0 = fminf(x0 * -SCALE_LOG2, nb0);
                    x1 = fminf(x1 * -SCALE_LOG2, nb1);
                    a0 = ex2(x0 - nb0);
                    a1 = ex2(x1 - nb1);
                    nb0 = x0;
                    nb1 = x1;
                    s0 = 0.f;
                    s1 = 0.f;
                    exp_range<0, 16>(S, nb0, nb1, s0, s1);
                } else {
                    x0 = fmaxf(__log2f(x0), 0.f);
                    x1 = fmaxf(__log2f(x1), 0.f);
                    a0 = ex2(-x0);
                    a1 = ex2(-x1);
                    nb0 -= x0;
                    nb1 -= x1;
                    s0 *= a0;
                    s1 *= a1;
#pragma unroll
                    for (int i = 0; i < 16; i++) {
                        S[4 * i] *= a0;
                        S[4 * i + 1] *= a0;
                        S[4 * i + 2] *= a1;
                        S[4 * i + 3] *= a1;
                    }
                }
                l0 *= a0;
                l1 *= a1;
            }
            l0 += s0;
            l1 += s1;
            if (!kok) mbar_wait(bar_full + 8 * slot, phase);
            wg_wait<0>();
            fence_f(O);
            fence_f(S);
            if (unext < uend) release(vslot);
#pragma unroll
            for (int i = 0; i < 32; i++) P[i] = pack_bf16(S[2 * i], S[2 * i + 1]);
            if (seg_end && unext < uend) {
                mbar_wait(bar_qfull + 8 * wg, (unext >> 4) & 1);
                if (u == 31) {
                    mbar_wait(bar_plan, 0);
                    get_plan();
                }
            }
            if (j == 0) {
                pack_o<0>(O, lp0, lp1);
                stsm_o<0>(O, stg + wg * (3 * 8192), stx);
                pack_o<1>(O, lp0, lp1);
                if (wg == 0) stsm_o<1>(O, stg + 8192, stx);
                asm volatile("fence.proxy.async.shared::cta;\n" ::: "memory");
                __syncwarp();
                if (lane <= 1 - wg) mbar_arrive(bar_ofull + 24 * wg + 8 * lane);
            }
            u = unext;
        }
        if (resc) rescale_o(O, a0, a1);
        bar_sync(mybar);
        fence_f(O);
        fence_u(P);
        issue_pv(O, P, (kvlo + slot * (SLOT_BYTES >> 4)) | VLBO, 1);
        if (wg == 0) bar_arrive(otherbar);
        const uint32_t tb0 = stg + wg * (3 * 8192);
        const uint32_t tb = wg ? stg - SM_STG + SM_KV + (slot == NSLOT - 1 ? 0 : slot + 1) * SLOT_BYTES - 8192 : stg;
        mbar_wait(bar_merge + 8 * wg, 0);
        uint32_t T[48];
        float k0 = 0.f, k1 = 0.f;
        if (uend & 15) {
            float2 t0, t1;
            const uint32_t st = sb + SM_STAT + (wg * 64 + wq * 16 + (lane >> 2)) * 8;
            asm volatile("ld.shared.v2.f32 {%0, %1}, [%2];\n" : "=f"(t0.x), "=f"(t0.y) : "r"(st) : "memory");
            asm volatile("ld.shared.v2.f32 {%0, %1}, [%2];\n" : "=f"(t1.x), "=f"(t1.y) : "r"(st + 64) : "memory");
            const float n0 = fminf(nb0, t0.x), n1 = fminf(nb1, t1.x);
            load_partial(T, tb0, tb, stx);
            l0 = quad_sum(l0);
            l1 = quad_sum(l1);
            k0 = t0.y * ex2(n0 - t0.x);
            k1 = t1.y * ex2(n1 - t1.x);
            const float c0 = ex2(n0 - nb0), c1 = ex2(n1 - nb1);
            l0 = __fdividef(1.0f, fmaf(l0, c0, k0));
            l1 = __fdividef(1.0f, fmaf(l1, c1, k1));
            k0 *= l0;
            k1 *= l1;
            l0 *= c0;
            l1 *= c1;
        } else {
            l0 = __fdividef(1.0f, quad_sum(l0));
            l1 = __fdividef(1.0f, quad_sum(l1));
#pragma unroll
            for (int i = 0; i < 48; i++) T[i] = 0u;
        }
        wg_wait<0>();
        fence_f(O);
        fence_u(P);
        finish_o<0>(O, T, l0, l1, k0, k1, tb0, stx, bar_ofull + 24 * wg, lane);
        sched_fence(zero);
        finish_o<1>(O, T, l0, l1, k0, k1, tb, stx, bar_ofull + 24 * wg, lane);
        sched_fence(zero);
        finish_o<2>(O, T, l0, l1, k0, k1, tb, stx, bar_ofull + 24 * wg, lane);
    }
}

typedef CUresult (*EncodeFn)(CUtensorMap*, CUtensorMapDataType, cuuint32_t, void*, const cuuint64_t*, const cuuint64_t*,
                             const cuuint32_t*, const cuuint32_t*, CUtensorMapInterleave, CUtensorMapSwizzle,
                             CUtensorMapL2promotion, CUtensorMapFloatOOBfill);

void make_map(EncodeFn fn, CUtensorMap* m, void* ptr, uint32_t box_rows) {
    cuuint64_t dims[2] = {(cuuint64_t)HD, (cuuint64_t)NHEAD * SEQ};
    cuuint64_t strides[1] = {(cuuint64_t)HD * 2};
    cuuint32_t box[2] = {64, box_rows};
    cuuint32_t es[2] = {1, 1};
    fn(m, CU_TENSOR_MAP_DATA_TYPE_BFLOAT16, 2, ptr, dims, strides, box, es, CU_TENSOR_MAP_INTERLEAVE_NONE,
       CU_TENSOR_MAP_SWIZZLE_128B, CU_TENSOR_MAP_L2_PROMOTION_L2_128B, CU_TENSOR_MAP_FLOAT_OOB_FILL_NONE);
}

void make_sched(Sched* sc, int ncl) {
    constexpr int NT = NTILES / CL;
    int s[MAXCL], e[MAXCL];
    const int ncut = (ncl == 64) ? 0 : NT - 3 * ncl;
    if (ncl == 64) {
        for (int i = 0; i < ncl; i++) { s[i] = 0; e[i] = 16; }
    } else {
        int n = 0;
        for (int c = 0; c < 8; c++)
            for (int v = 0; v <= 14;) {
                const int step = (c < 2 && (v == 6 || v == 7)) ? 1 : 2;
                s[n] = v;
                e[n] = 16 - v - step;
                n++;
                v += step;
            }
    }
    int ord[MAXCL];
    for (int i = 0; i < ncl; i++) ord[i] = i;
    auto cost = [&](int i) { return (s[i] + e[i]) * 100 + (s[i] ? 20 : 0) + (e[i] ? 25 : 0) + (s[i] == 2 ? 10 : 0) + (e[i] == 2 ? 10 : 0); };
    for (int i = 1; i < ncl; i++)
        for (int k = i; k > 0 && cost(ord[k]) > cost(ord[k - 1]); k--) { const int t = ord[k]; ord[k] = ord[k - 1]; ord[k - 1] = t; }
    int cutid[MAXCL + 1] = {0}, fullid[MAXCL], id = 2 * ncl;
    for (int pass = 0; pass < 17; pass++) {
        const int v = pass ? pass - 1 : -1;
        for (int i = 0; i < ncl; i++)
            if (s[i] && (pass ? (s[i] == v && !(v & 1)) : (s[i] & 1))) cutid[i] = id++;
        for (int i = 0; i < ncl; i++)
            if (pass ? (s[i] == v && !(v & 1)) : (s[i] & 1)) fullid[i] = id++;
    }
    for (int k = 0; k < ncl; k++) {
        const int i = ord[k];
        unsigned long long w = 0;
        int seg = 2;
        if (s[i]) w |= (unsigned long long)cutid[i] << (8 * seg++);
        w |= (unsigned long long)fullid[i] << (8 * seg++);
        if (e[i]) w |= (unsigned long long)(ncut ? cutid[i + 1] : id++) << (8 * seg);
        w |= (unsigned long long)(s[i] ? 31 + s[i] : 0) << 40;
        w |= (unsigned long long)(16 * seg + e[i]) << 48;
        w |= (unsigned long long)((16 - e[i]) & 15) << 56;
        w |= (unsigned long long)((2 * (48 + s[i] + e[i]) - 3) % NSLOT) << 60;
        sc->w[k] = w;
    }
}

}

extern "C" void kernel_launch(void* const* d_in, const int* in_sizes, int n_in, void* d_out, int out_size) {
    (void)in_sizes; (void)n_in; (void)out_size;
    static EncodeFn enc = nullptr;
    static Sched sched;
    static int ncl = 64;
    const bool first = !enc;
    if (first) {
        void* fp = nullptr;
        cudaDriverEntryPointQueryResult qr;
        cudaGetDriverEntryPoint("cuTensorMapEncodeTiled", &fp, cudaEnableDefault, &qr);
        enc = (EncodeFn)fp;
        cudaFuncSetAttribute(fa_fwd_kernel, cudaFuncAttributeMaxDynamicSharedMemorySize, SMEM_BYTES);
    }
    CUtensorMap mq, mk, mv, mo;
    make_map(enc, &mq, d_in[0], 64);
    make_map(enc, &mk, d_in[1], BN / CL);
    make_map(enc, &mv, d_in[2], BN / CL);
    make_map(enc, &mo, d_out, 64);

    cudaLaunchConfig_t cfg = {};
    cfg.gridDim = dim3(MAXCL * CL, 1, 1);
    cfg.blockDim = dim3(NTHREADS, 1, 1);
    cfg.dynamicSmemBytes = SMEM_BYTES;
    cfg.stream = cudaStreamPerThread;
    cudaLaunchAttribute attr[1];
    attr[0].id = cudaLaunchAttributeClusterDimension;
    attr[0].val.clusterDim.x = CL;
    attr[0].val.clusterDim.y = 1;
    attr[0].val.clusterDim.z = 1;
    cfg.attrs = attr;
    cfg.numAttrs = 1;
    if (first) {
        int nact = 0;
        if (cudaOccupancyMaxActiveClusters(&nact, fa_fwd_kernel, &cfg) != cudaSuccess) { (void)cudaGetLastError(); nact = 0; }
        ncl = (nact >= MAXCL) ? MAXCL : 64;
        make_sched(&sched, ncl);
    }
    cfg.gridDim = dim3(ncl * CL, 1, 1);
    cudaLaunchKernelEx(&cfg, fa_fwd_kernel, mq, mk, mv, mo, sched, (const __nv_bfloat16*)d_in[0], (const __nv_bfloat16*)d_in[1],
                       (const __nv_bfloat16*)d_out, 0);
}
```
